```python
import torch

def _softmax(x, axis=-1):
    return torch.softmax(x, dim=axis)
def _gelu(x):
    return torch.nn.functional.gelu(x, approximate="tanh")
def _silu(x):
    return torch.nn.functional.silu(x)
def _sigmoid(x):
    return torch.sigmoid(x)
def _layernorm(x, axis=-1, eps=1e-5):
    m = x.mean(dim=axis, keepdim=True)
    v = x.var(dim=axis, keepdim=True, unbiased=False)
    return (x - m) / torch.sqrt(v + eps)
def _scatter_add(tgt, idx, src, axis=0):
    return tgt.clone().index_add_(axis, idx, src)
def _segment_sum(src, seg, n):
    out = torch.zeros((n,) + src.shape[1:], dtype=src.dtype)
    return out.index_add_(0, seg, src)
def _pad(x, pw):
    flat = tuple(v for pair in reversed(pw) for v in pair)
    return torch.nn.functional.pad(x, flat)

kernel_name = 'recurrent_scan__ssm_conv_s4__glu_gated_glu__prompt'

def setup_inputs():

    _w = (lambda a: (lambda t: t.to(torch.bfloat16) if t.is_floating_point() else t)(torch.as_tensor(a)))
    def _A_setup():
        B, L, D, N = 1, 2048, 512, 128
        A_re = -(lambda _x: torch.exp(torch.as_tensor(_x)))((lambda *s: torch.randn(*s, dtype=torch.bfloat16) * 6.4)(D, N))
        A_im = torch.pi * (lambda *s: torch.randn(*s, dtype=torch.bfloat16) * 0.05)(D, N)
        B_re = (lambda *s: torch.randn(*s, dtype=torch.bfloat16) * 0.1)(D, N)
        B_im = (lambda *s: torch.randn(*s, dtype=torch.bfloat16) * 0.1)(D, N)
        C_re = (lambda *s: torch.randn(*s, dtype=torch.bfloat16) * 0.1)(D, N)
        C_im = (lambda *s: torch.randn(*s, dtype=torch.bfloat16) * 0.1)(D, N)
        log_dt = (lambda *s: torch.randn(*s, dtype=torch.bfloat16) * 0.05)(D) * 0.5 - 4.0
        Dskip = (lambda *s: torch.randn(*s, dtype=torch.bfloat16) * 0.05)(D)
        return {
            "u": _w((lambda *s: torch.randn(*s, dtype=torch.bfloat16) * 0.05)(B, L, D)),
            "A_re": _w(A_re),
            "A_im": _w(A_im),
            "B_re": _w(B_re),
            "B_im": _w(B_im),
            "C_re": _w(C_re),
            "C_im": _w(C_im),
            "log_dt": _w(log_dt),
            "Dskip": _w(Dskip),
        }
    _A_in = _A_setup()

    def _B_setup():
        B, S, D, F = 1, 2048, 512, 1376
        return {
            "x": _w((lambda *s: torch.randn(*s, dtype=torch.bfloat16) * 0.05)(B, S, D)),
            "w_gate": _w((lambda *s: torch.randn(*s, dtype=torch.bfloat16) * 0.05)(D, F)),
            "w_up": _w((lambda *s: torch.randn(*s, dtype=torch.bfloat16) * 0.05)(D, F)),
            "w_down": _w((lambda *s: torch.randn(*s, dtype=torch.bfloat16) * 0.05)(F, D)),
        }
    _B_in = _B_setup()

    return {
        "A_u": _A_in["u"],
        "A_A_re": _A_in["A_re"],
        "A_A_im": _A_in["A_im"],
        "A_B_re": _A_in["B_re"],
        "A_B_im": _A_in["B_im"],
        "A_C_re": _A_in["C_re"],
        "A_C_im": _A_in["C_im"],
        "A_log_dt": _A_in["log_dt"],
        "A_Dskip": _A_in["Dskip"],
        "B_x": _B_in["x"],
        "B_w_gate": _B_in["w_gate"],
        "B_w_up": _B_in["w_up"],
        "B_w_down": _B_in["w_down"],
    }

def reference(A_u, A_A_re, A_A_im, A_B_re, A_B_im, A_C_re, A_C_im, A_log_dt, A_Dskip, B_x, B_w_gate, B_w_up, B_w_down):
    def _A_ref(u, A_re, A_im, B_re, B_im, C_re, C_im, log_dt, Dskip):
        Bsz, L, D = u.shape
        dt = torch.exp(log_dt)[:, None]
        A = A_re + 1j * A_im
        Bc = B_re + 1j * B_im
        Cc = C_re + 1j * C_im
        logdA = dt * A
        dB = dt * Bc
        l = (lambda x, dt: x.to(dt))(torch.arange(L), A_re.dtype)
        P = torch.exp(logdA[:, :, None] * l[None, None, :])
        K = torch.einsum("dn,dnl,dn->dl", Cc, P, dB).real
        L2 = 2 * L
        Kp = _pad(K, ((0, 0), (0, L)))
        up = (lambda x, *d: x.permute(*d))(u, 0, 2, 1)
        up = _pad(up, ((0, 0), (0, 0), (0, L)))
        Kf = (lambda x, axes=(-2,-1): torch.fft.rfft2(x.float(), dim=axes))(Kp[:, None, :], axes=(-2, -1))
        Uf = (lambda x, axes=(-2,-1): torch.fft.rfft2(x.float(), dim=axes))(up[:, :, None, :], axes=(-2, -1))
        Yf = Uf * Kf[None, :, :, :]
        y = (lambda x, s, axes=(-2,-1): torch.fft.irfft2(x, s=s, dim=axes).to(torch.bfloat16))(Yf, (1, L2), axes=(-2, -1))[:, :, 0, :L]
        y = (lambda x, *d: x.permute(*d))(y, 0, 2, 1) + u * Dskip[None, None, :]
        return y

    def _B_ref(x, w_gate, w_up, w_down):
        g = torch.einsum("bsd,df->bsf", x, w_gate)
        u = torch.einsum("bsd,df->bsf", x, w_up)
        h = _sigmoid(g) * u
        return torch.einsum("bsf,fd->bsd", h, w_down)

    x = A_u
    xn = _layernorm(x, axis=-1)
    s = _A_ref(xn, A_A_re, A_A_im, A_B_re, A_B_im, A_C_re, A_C_im, A_log_dt, A_Dskip)
    g = _silu(_B_ref(xn, B_w_gate, B_w_up, B_w_down))
    return x + s * g
```

```cpp
#include <cuda_runtime.h>
#include <cuda.h>
#include <cuda_bf16.h>
#include <cuda_fp16.h>
#include <stdint.h>

namespace {

constexpr int T_ = 2048, D_ = 512, F_ = 1376;
constexpr int TB = 171;
constexpr uint32_t G1_STG = 55296;
constexpr uint32_t G1_TX = 4 * 8192 + TB * 128;
constexpr uint32_t RING = 3 * G1_STG;
constexpr uint32_t STAGING = RING - 2 * 22528;
constexpr uint32_t AUX = RING;
constexpr uint32_t XA = 5120;
constexpr uint32_t CH0 = AUX + 4 * XA, CHS = 11008;
constexpr uint32_t STATS = CH0 + 4 * CHS;
constexpr uint32_t BARS = STATS + 1408;
constexpr uint32_t SMEM_BYTES = BARS + 384;
constexpr uint32_t C_P01 = 6528, C_P2 = C_P01 + 2560, C_P3 = C_P2 + 1024, C_KS = C_P3 + 640, C_KD = 4352;
constexpr uint32_t WPL1 = 1600, WPL0 = 1088;
constexpr uint32_t ZONE = 2 * 16384, ZCH = 4 * WPL0;
constexpr uint32_t HRING = 5 * 16384;
constexpr uint32_t Y3 = ZONE + 4 * ZCH, Y3CH = 6528;
constexpr uint32_t XSLOT = AUX + 32768;
constexpr int G2P1 = 4, DENSE_A = 3;
constexpr uint32_t KST = 53 * 144;
enum { B_G1F = 0, B_XS = 3, B_RECV = 4, B_X = 5,
       B_G2F = 9, B_G1E = 15, B_G2E = 18, B_STG = 23, B_PEER = 24, B_AUXD = 25, B_Z = 26, B_Y = 27,
       B_STATS = 28, B_TAB = 29, B_EPI = 30, B_SD = 36, B_LN = 38, B_Y3 = 39,
       B_KD = 40, B_COUNT = 41 };
enum { C_LN = 0, C_H = 1, C_S = 25, C_DONE = 33, C_COUNT = 34 };

__device__ __align__(1024) __nv_bfloat16 g_h[22 * T_ * 64];
__device__ __align__(1024) __nv_bfloat16 g_xnT[D_ * T_];
__device__ __align__(1024) __nv_bfloat16 g_sT[D_ * T_];
__device__ __align__(1024) float2 g_stats[T_];
__device__ __align__(1024) uint8_t g_w79[D_ * ZCH];
__device__ __align__(1024) unsigned g_cnt[C_COUNT * 32];

struct Params {
  const __nv_bfloat16 *ssm[6], *logdt, *x, *dskip, *wdp;
  __nv_bfloat16* out;
  uint32_t zero;
  CUtensorMap x1, wg, wu, xt, wd, x2, st, xl, ss;
};

__device__ __forceinline__ uint32_t smem_u32(const void* p) { return (uint32_t)__cvta_generic_to_shared(p); }
__device__ __forceinline__ void mbar_init(uint32_t bar, int cnt) { asm volatile("mbarrier.init.shared::cta.b64 [%0], %1;" ::"r"(bar), "r"(cnt)); }
__device__ __forceinline__ void mbar_expect_tx(uint32_t bar, uint32_t bytes) { asm volatile("mbarrier.arrive.expect_tx.shared::cta.b64 _, [%0], %1;" ::"r"(bar), "r"(bytes) : "memory"); }
__device__ __forceinline__ void mbar_arrive(uint32_t bar) { asm volatile("mbarrier.arrive.shared::cta.b64 _, [%0];" ::"r"(bar) : "memory"); }
__device__ __forceinline__ bool mbar_try(uint32_t bar, uint32_t parity) {
  uint32_t ok;
  asm volatile("{\n.reg .pred p;\nmbarrier.try_wait.parity.shared::cta.b64 p, [%1], %2;\nselp.u32 %0,1,0,p;\n}" : "=r"(ok) : "r"(bar), "r"(parity) : "memory");
  return ok;
}
__device__ __forceinline__ void mbar_wait(uint32_t bar, uint32_t parity) {
  for (int it = 0; it < (1 << 18) && !mbar_try(bar, parity); ++it) {}
}
__device__ __forceinline__ bool mbar_try_cl(uint32_t bar, uint32_t parity) {
  uint32_t ok;
  asm volatile("{\n.reg .pred p;\nmbarrier.try_wait.parity.relaxed.cluster.shared::cta.b64 p, [%1], %2;\nselp.u32 %0,1,0,p;\n}" : "=r"(ok) : "r"(bar), "r"(parity) : "memory");
  return ok;
}
__device__ __forceinline__ void mbar_wait_cl(uint32_t bar, uint32_t parity) {
  for (int it = 0; it < (1 << 18) && !mbar_try_cl(bar, parity); ++it) {}
  asm volatile("fence.acquire.sync_restrict::shared::cluster.cluster;" ::: "memory");
}
__device__ __forceinline__ uint32_t mapa(uint32_t addr, uint32_t cta) {
  uint32_t r;
  asm volatile("mapa.shared::cluster.u32 %0, %1, %2;" : "=r"(r) : "r"(addr), "r"(cta));
  return r;
}
__device__ __forceinline__ void tma2d(uint32_t dst, const CUtensorMap* m, uint32_t bar, int c0, int c1) {
  asm volatile("cp.async.bulk.tensor.2d.shared::cluster.global.mbarrier::complete_tx::bytes [%0], [%1, {%3,%4}], [%2];" ::"r"(dst), "l"(m), "r"(bar), "r"(c0), "r"(c1) : "memory");
}
__device__ __forceinline__ void tma2d_store(const CUtensorMap* m, uint32_t src, int c0, int c1) {
  asm volatile("cp.async.bulk.tensor.2d.global.shared::cta.bulk_group [%0, {%2,%3}], [%1];" ::"l"(m), "r"(src), "r"(c0), "r"(c1) : "memory");
}
__device__ __forceinline__ void bulk_commit() { asm volatile("cp.async.bulk.commit_group;" ::: "memory"); }
__device__ __forceinline__ void bulk_wait0() { asm volatile("cp.async.bulk.wait_group 0;" ::: "memory"); }
__device__ __forceinline__ void bulk_wait0_read() { asm volatile("cp.async.bulk.wait_group.read 0;" ::: "memory"); }
__device__ __forceinline__ void fence_async_smem() { asm volatile("fence.proxy.async.shared::cta;" ::: "memory"); }
__device__ __forceinline__ void fence_async_global() { asm volatile("fence.proxy.async.global;" ::: "memory"); }
__device__ __forceinline__ void red_arrive(unsigned* p) { asm volatile("red.relaxed.gpu.global.add.u32 [%0], 1;" ::"l"(p) : "memory"); }
__device__ __forceinline__ void poll_ge(const unsigned* p, const unsigned* q, unsigned target) {
  for (int it = 0; it < (1 << 15); ++it) {
    unsigned v, w;
    asm volatile("ld.acquire.gpu.global.u32 %0, [%2];\n\tld.acquire.gpu.global.u32 %1, [%3];" : "=r"(v), "=r"(w) : "l"(p), "l"(q) : "memory");
    if (min(v, w) >= target) break;
  }
}
__device__ __forceinline__ void poll_ge(const unsigned* p, unsigned target) {
  for (int it = 0; it < (1 << 15); ++it) {
    unsigned v;
    asm volatile("ld.acquire.gpu.global.u32 %0, [%1];" : "=r"(v) : "l"(p) : "memory");
    if (v >= target) break;
  }
}
template <int ID, int N>
__device__ __forceinline__ void named_bar() { asm volatile("bar.sync %0, %1;" ::"n"(ID), "n"(N) : "memory"); }
__device__ __forceinline__ void wg_bar(int wg) { if (wg) named_bar<3, 128>(); else named_bar<2, 128>(); }
__device__ __forceinline__ void cluster_wait() { asm volatile("barrier.cluster.wait.aligned;" ::: "memory"); }
__device__ __forceinline__ bool elect() {
  uint32_t p;
  asm volatile("{\n.reg .pred q;\nelect.sync _|q, 0xffffffff;\nselp.u32 %0,1,0,q;\n}" : "=r"(p));
  return p;
}
__device__ __forceinline__ uint64_t mkdesc(uint32_t addr, uint32_t lbo, uint32_t sbo) {
  return (uint64_t)((addr & 0x3FFFF) >> 4) | ((uint64_t)(lbo >> 4) << 16) | ((uint64_t)(sbo >> 4) << 32) | (1ull << 62);
}
#define WG_FENCE() asm volatile("wgmma.fence.sync.aligned;" ::: "memory")
#define WG_COMMIT() asm volatile("wgmma.commit_group.sync.aligned;" ::: "memory")
#define WG_WAIT(n) asm volatile("wgmma.wait_group.sync.aligned %0;" ::"n"(n) : "memory")
template <int N>
__device__ __forceinline__ void fence_regs(float (&d)[N]) {
#pragma unroll
  for (int j = 0; j < N; j++) asm volatile("" : "+f"(d[j])::"memory");
}
template<int TA, int TB> __device__ __forceinline__ void wgmma_ss_n176(float (&d)[88], uint64_t da, uint64_t db, int scale_d) {
  asm volatile("{\n.reg .pred p;\nsetp.ne.b32 p, %90, 0;\n"
    "wgmma.mma_async.sync.aligned.m64n176k16.f32.bf16.bf16 {%0, %1, %2, %3, %4, %5, %6, %7, %8, %9, %10, %11, %12, %13, %14, %15, %16, %17, %18, %19, %20, %21, %22, %23, %24, %25, %26, %27, %28, %29, %30, %31, %32, %33, %34, %35, %36, %37, %38, %39, %40, %41, %42, %43, %44, %45, %46, %47, %48, %49, %50, %51, %52, %53, %54, %55, %56, %57, %58, %59, %60, %61, %62, %63, %64, %65, %66, %67, %68, %69, %70, %71, %72, %73, %74, %75, %76, %77, %78, %79, %80, %81, %82, %83, %84, %85, %86, %87}, %88, %89, p, 1, 1, %91, %92;\n}\n"
    : "+f"(d[0]), "+f"(d[1]), "+f"(d[2]), "+f"(d[3]), "+f"(d[4]), "+f"(d[5]), "+f"(d[6]), "+f"(d[7]), "+f"(d[8]), "+f"(d[9]), "+f"(d[10]), "+f"(d[11]), "+f"(d[12]), "+f"(d[13]), "+f"(d[14]), "+f"(d[15]), "+f"(d[16]), "+f"(d[17]), "+f"(d[18]), "+f"(d[19]), "+f"(d[20]), "+f"(d[21]), "+f"(d[22]), "+f"(d[23]), "+f"(d[24]), "+f"(d[25]), "+f"(d[26]), "+f"(d[27]), "+f"(d[28]), "+f"(d[29]), "+f"(d[30]), "+f"(d[31]), "+f"(d[32]), "+f"(d[33]), "+f"(d[34]), "+f"(d[35]), "+f"(d[36]), "+f"(d[37]), "+f"(d[38]), "+f"(d[39]), "+f"(d[40]), "+f"(d[41]), "+f"(d[42]), "+f"(d[43]), "+f"(d[44]), "+f"(d[45]), "+f"(d[46]), "+f"(d[47]), "+f"(d[48]), "+f"(d[49]), "+f"(d[50]), "+f"(d[51]), "+f"(d[52]), "+f"(d[53]), "+f"(d[54]), "+f"(d[55]), "+f"(d[56]), "+f"(d[57]), "+f"(d[58]), "+f"(d[59]), "+f"(d[60]), "+f"(d[61]), "+f"(d[62]), "+f"(d[63]), "+f"(d[64]), "+f"(d[65]), "+f"(d[66]), "+f"(d[67]), "+f"(d[68]), "+f"(d[69]), "+f"(d[70]), "+f"(d[71]), "+f"(d[72]), "+f"(d[73]), "+f"(d[74]), "+f"(d[75]), "+f"(d[76]), "+f"(d[77]), "+f"(d[78]), "+f"(d[79]), "+f"(d[80]), "+f"(d[81]), "+f"(d[82]), "+f"(d[83]), "+f"(d[84]), "+f"(d[85]), "+f"(d[86]), "+f"(d[87])
    : "l"(da), "l"(db), "r"(scale_d), "n"(TA), "n"(TB));
}
template<int TA, int TB> __device__ __forceinline__ void wgmma_ss_n128(float (&d)[64], uint64_t da, uint64_t db, int scale_d) {
  asm volatile("{\n.reg .pred p;\nsetp.ne.b32 p, %66, 0;\n"
    "wgmma.mma_async.sync.aligned.m64n128k16.f32.bf16.bf16 {%0, %1, %2, %3, %4, %5, %6, %7, %8, %9, %10, %11, %12, %13, %14, %15, %16, %17, %18, %19, %20, %21, %22, %23, %24, %25, %26, %27, %28, %29, %30, %31, %32, %33, %34, %35, %36, %37, %38, %39, %40, %41, %42, %43, %44, %45, %46, %47, %48, %49, %50, %51, %52, %53, %54, %55, %56, %57, %58, %59, %60, %61, %62, %63}, %64, %65, p, 1, 1, %67, %68;\n}\n"
    : "+f"(d[0]), "+f"(d[1]), "+f"(d[2]), "+f"(d[3]), "+f"(d[4]), "+f"(d[5]), "+f"(d[6]), "+f"(d[7]), "+f"(d[8]), "+f"(d[9]), "+f"(d[10]), "+f"(d[11]), "+f"(d[12]), "+f"(d[13]), "+f"(d[14]), "+f"(d[15]), "+f"(d[16]), "+f"(d[17]), "+f"(d[18]), "+f"(d[19]), "+f"(d[20]), "+f"(d[21]), "+f"(d[22]), "+f"(d[23]), "+f"(d[24]), "+f"(d[25]), "+f"(d[26]), "+f"(d[27]), "+f"(d[28]), "+f"(d[29]), "+f"(d[30]), "+f"(d[31]), "+f"(d[32]), "+f"(d[33]), "+f"(d[34]), "+f"(d[35]), "+f"(d[36]), "+f"(d[37]), "+f"(d[38]), "+f"(d[39]), "+f"(d[40]), "+f"(d[41]), "+f"(d[42]), "+f"(d[43]), "+f"(d[44]), "+f"(d[45]), "+f"(d[46]), "+f"(d[47]), "+f"(d[48]), "+f"(d[49]), "+f"(d[50]), "+f"(d[51]), "+f"(d[52]), "+f"(d[53]), "+f"(d[54]), "+f"(d[55]), "+f"(d[56]), "+f"(d[57]), "+f"(d[58]), "+f"(d[59]), "+f"(d[60]), "+f"(d[61]), "+f"(d[62]), "+f"(d[63])
    : "l"(da), "l"(db), "r"(scale_d), "n"(TA), "n"(TB));
}
template<int TA, int TB> __device__ __forceinline__ void wgmma_ss_n64(float (&d)[32], uint64_t da, uint64_t db, int scale_d) {
  asm volatile("{\n.reg .pred p;\nsetp.ne.b32 p, %34, 0;\n"
    "wgmma.mma_async.sync.aligned.m64n64k16.f32.bf16.bf16 {%0, %1, %2, %3, %4, %5, %6, %7, %8, %9, %10, %11, %12, %13, %14, %15, %16, %17, %18, %19, %20, %21, %22, %23, %24, %25, %26, %27, %28, %29, %30, %31}, %32, %33, p, 1, 1, %35, %36;\n}\n"
    : "+f"(d[0]), "+f"(d[1]), "+f"(d[2]), "+f"(d[3]), "+f"(d[4]), "+f"(d[5]), "+f"(d[6]), "+f"(d[7]), "+f"(d[8]), "+f"(d[9]), "+f"(d[10]), "+f"(d[11]), "+f"(d[12]), "+f"(d[13]), "+f"(d[14]), "+f"(d[15]), "+f"(d[16]), "+f"(d[17]), "+f"(d[18]), "+f"(d[19]), "+f"(d[20]), "+f"(d[21]), "+f"(d[22]), "+f"(d[23]), "+f"(d[24]), "+f"(d[25]), "+f"(d[26]), "+f"(d[27]), "+f"(d[28]), "+f"(d[29]), "+f"(d[30]), "+f"(d[31])
    : "l"(da), "l"(db), "r"(scale_d), "n"(TA), "n"(TB));
}
template<int TB> __device__ __forceinline__ void wgmma_rs_n32(float (&d)[16], uint32_t a0, uint32_t a1, uint32_t a2, uint32_t a3, uint64_t db, int scale_d) {
  asm volatile("{\n.reg .pred p;\nsetp.ne.b32 p, %21, 0;\n"
    "wgmma.mma_async.sync.aligned.m64n32k16.f32.bf16.bf16 {%0, %1, %2, %3, %4, %5, %6, %7, %8, %9, %10, %11, %12, %13, %14, %15}, {%16,%17,%18,%19}, %20, p, 1, 1, %22;\n}\n"
    : "+f"(d[0]), "+f"(d[1]), "+f"(d[2]), "+f"(d[3]), "+f"(d[4]), "+f"(d[5]), "+f"(d[6]), "+f"(d[7]), "+f"(d[8]), "+f"(d[9]), "+f"(d[10]), "+f"(d[11]), "+f"(d[12]), "+f"(d[13]), "+f"(d[14]), "+f"(d[15])
    : "r"(a0), "r"(a1), "r"(a2), "r"(a3), "l"(db), "r"(scale_d), "n"(TB));
}

__device__ __forceinline__ void ldsm4(uint32_t (&r)[4], uint32_t addr) {
  asm volatile("ldmatrix.sync.aligned.m8n8.x4.shared.b16 {%0,%1,%2,%3},[%4];" : "=r"(r[0]), "=r"(r[1]), "=r"(r[2]), "=r"(r[3]) : "r"(addr) : "memory");
}
__device__ __forceinline__ void ldsm4t(uint32_t (&r)[4], uint32_t addr) {
  asm volatile("ldmatrix.sync.aligned.m8n8.x4.trans.shared.b16 {%0,%1,%2,%3},[%4];" : "=r"(r[0]), "=r"(r[1]), "=r"(r[2]), "=r"(r[3]) : "r"(addr) : "memory");
}
__device__ __forceinline__ void stsm4(uint32_t addr, uint32_t r0, uint32_t r1, uint32_t r2, uint32_t r3) {
  asm volatile("stmatrix.sync.aligned.m8n8.x4.shared.b16 [%0], {%1,%2,%3,%4};" ::"r"(addr), "r"(r0), "r"(r1), "r"(r2), "r"(r3) : "memory");
}
__device__ __forceinline__ void stsm4t(uint32_t addr, uint32_t r0, uint32_t r1, uint32_t r2, uint32_t r3) {
  asm volatile("stmatrix.sync.aligned.m8n8.x4.trans.shared.b16 [%0], {%1,%2,%3,%4};" ::"r"(addr), "r"(r0), "r"(r1), "r"(r2), "r"(r3) : "memory");
}
__device__ __forceinline__ uint32_t lds32(uint32_t a) { uint32_t v; asm volatile("ld.shared.u32 %0, [%1];" : "=r"(v) : "r"(a) : "memory"); return v; }
__device__ __forceinline__ float lds32f(uint32_t a) { float v; asm volatile("ld.shared.f32 %0, [%1];" : "=f"(v) : "r"(a) : "memory"); return v; }
__device__ __forceinline__ void sts32f(uint32_t a, float v) { asm volatile("st.shared.f32 [%0], %1;" ::"r"(a), "f"(v) : "memory"); }
__device__ __forceinline__ void prefetch_map(const CUtensorMap* m) { asm volatile("prefetch.tensormap [%0];" ::"l"(m) : "memory"); }
__device__ __forceinline__ float lds16bf(uint32_t a) { uint16_t v; asm volatile("ld.shared.u16 %0, [%1];" : "=h"(v) : "r"(a) : "memory"); return __uint_as_float((uint32_t)v << 16); }
__device__ __forceinline__ uint4 lds128(uint32_t a) { uint4 v; asm volatile("ld.shared.v4.u32 {%0,%1,%2,%3}, [%4];" : "=r"(v.x), "=r"(v.y), "=r"(v.z), "=r"(v.w) : "r"(a) : "memory"); return v; }
__device__ __forceinline__ float4 lds128f(uint32_t a) { float4 v; asm volatile("ld.shared.v4.f32 {%0,%1,%2,%3}, [%4];" : "=f"(v.x), "=f"(v.y), "=f"(v.z), "=f"(v.w) : "r"(a) : "memory"); return v; }
__device__ __forceinline__ void sts16(uint32_t a, uint16_t v) { asm volatile("st.shared.u16 [%0], %1;" ::"r"(a), "h"(v) : "memory"); }
__device__ __forceinline__ void sts32(uint32_t a, uint32_t v) { asm volatile("st.shared.u32 [%0], %1;" ::"r"(a), "r"(v) : "memory"); }
__device__ __forceinline__ void sts64f(uint32_t a, float x, float y) { asm volatile("st.shared.v2.f32 [%0], {%1,%2};" ::"r"(a), "f"(x), "f"(y) : "memory"); }
__device__ __forceinline__ void sts128(uint32_t a, uint4 v) { asm volatile("st.shared.v4.u32 [%0], {%1,%2,%3,%4};" ::"r"(a), "r"(v.x), "r"(v.y), "r"(v.z), "r"(v.w) : "memory"); }
__device__ __forceinline__ uint32_t pack2(float lo, float hi) { uint32_t r; asm("cvt.rn.bf16x2.f32 %0, %1, %2;" : "=r"(r) : "f"(hi), "f"(lo)); return r; }
__device__ __forceinline__ float bflo(uint32_t v) { return __uint_as_float(v << 16); }
__device__ __forceinline__ float bfhi(uint32_t v) { return __uint_as_float(v & 0xffff0000u); }
__device__ __forceinline__ float bfr(float v) { return __bfloat162float(__float2bfloat16_rn(v)); }
__device__ __forceinline__ float tanh_fast(float v) { float r; asm("tanh.approx.f32 %0, %1;" : "=f"(r) : "f"(v)); return r; }

__device__ __forceinline__ void mma16816h(float (&c)[4], const uint32_t (&a)[4], uint32_t b0, uint32_t b1) {
  asm volatile("mma.sync.aligned.m16n8k16.row.col.f32.f16.f16.f32 {%0,%1,%2,%3},{%4,%5,%6,%7},{%8,%9},{%0,%1,%2,%3};"
               : "+f"(c[0]), "+f"(c[1]), "+f"(c[2]), "+f"(c[3]) : "r"(a[0]), "r"(a[1]), "r"(a[2]), "r"(a[3]), "r"(b0), "r"(b1));
}
struct HZ { __half2 z, iz; };
__device__ __forceinline__ __half2 hmul(__half2 a, const HZ& b) { return __hfma2(__low2half2(a), b.z, __hmul2(__high2half2(a), b.iz)); }
struct C2 { float x, y; };
__device__ __forceinline__ __half2 toh(C2 a) { return __floats2half2_rn(a.x, a.y); }
__device__ __forceinline__ HZ tohz(C2 a) { return {__floats2half2_rn(a.x, a.y), __floats2half2_rn(-a.y, a.x)}; }
__device__ __forceinline__ HZ tohzc(C2 a) { return {__floats2half2_rn(a.x, -a.y), __floats2half2_rn(a.y, a.x)}; }
__device__ __forceinline__ C2 cmul(C2 a, C2 b) { return {fmaf(a.x, b.x, -a.y * b.y), fmaf(a.x, b.y, a.y * b.x)}; }
__device__ __forceinline__ C2 csqr(C2 a) { return {fmaf(a.x, a.x, -a.y * a.y), (a.x + a.x) * a.y}; }
__device__ __forceinline__ C2 cexp_p(float al, float wr, float p) {
  float m;
  asm("ex2.approx.ftz.f32 %0, %1;" : "=f"(m) : "f"(al * p));
  float u = wr * p;
  float f = (u - (fabsf(u) < 4194304.f ? __fadd_rn(__fadd_rn(u, 12582912.f), -12582912.f) : u)) * 6.283185307179586f;
  return {m * __cosf(f), m * __sinf(f)};
}
__device__ __forceinline__ uint32_t xof(uint32_t unit) { return (unit ^ ((unit >> 3) & 7)) << 4; }
template <uint32_t PL>
__device__ __forceinline__ uint32_t wof(uint32_t unit) { return (unit & 1) * PL + (unit >> 1) * 16; }
__device__ __forceinline__ uint32_t copy_reg(uint32_t a, uint32_t zero) { uint32_t d; asm volatile("add.rn.bf16x2 %0, %1, %2;" : "=r"(d) : "r"(a), "r"(zero)); return d; }
__device__ __forceinline__ uint32_t hadd(uint32_t a, uint32_t b) { uint32_t d; asm("add.rn.bf16x2 %0, %1, %2;" : "=r"(d) : "r"(a), "r"(b)); return d; }
__device__ __forceinline__ uint32_t hsub(uint32_t a, uint32_t b) { uint32_t d; asm("sub.rn.bf16x2 %0, %1, %2;" : "=r"(d) : "r"(a), "r"(b)); return d; }
__device__ __forceinline__ uint32_t mid(uint32_t a, uint32_t b) { return __byte_perm(a, b, 0x5432); }
__device__ __forceinline__ void unpack8(float* f, uint4 v) {
  f[0] = bflo(v.x); f[1] = bfhi(v.x); f[2] = bflo(v.y); f[3] = bfhi(v.y);
  f[4] = bflo(v.z); f[5] = bfhi(v.z); f[6] = bflo(v.w); f[7] = bfhi(v.w);
}
__device__ __forceinline__ void load_quad(uint32_t (&q)[4], uint32_t p) {
  q[0] = lds32(p + 32); q[1] = lds32(p + 64); q[2] = lds32(p); q[3] = lds32(p + 32);
}
__device__ __forceinline__ void mmaq(float (&c)[4], const uint32_t (&q)[4], uint32_t b0, uint32_t b1) {
  asm volatile("mma.sync.aligned.m16n8k16.row.col.f32.bf16.bf16.f32 {%0,%1,%2,%3},{%4,%5,%6,%7},{%8,%9},{%0,%1,%2,%3};"
               : "+f"(c[0]), "+f"(c[1]), "+f"(c[2]), "+f"(c[3]) : "r"(q[0]), "r"(q[1]), "r"(q[2]), "r"(q[3]), "r"(b0), "r"(b1));
}

template <int D0, int ND>
__device__ __forceinline__ void phase_mma(float (&acc)[6][4], uint32_t ptab, uint32_t a0) {
  uint32_t Q[ND][4], b[(8 - D0) / 2][4];
#pragma unroll
  for (int i = 0; i < ND; i++) load_quad(Q[i], ptab + 64 * i);
#pragma unroll
  for (int i = 0; i < (8 - D0) / 2; i++) ldsm4t(b[i], a0 + 512 * i);
#pragma unroll
  for (int dd = 0; dd < ND; dd++)
#pragma unroll
    for (int kap = 0; kap + D0 + dd < 8; kap++) mmaq(acc[kap + D0 + dd - 2], Q[dd], b[kap >> 1][2 * (kap & 1)], b[kap >> 1][2 * (kap & 1) + 1]);
}

__global__ void __launch_bounds__(512, 1) fused_kernel(const __grid_constant__ Params P) {
  extern __shared__ __align__(1024) uint8_t smem_raw[];
  const uint32_t sb = smem_u32(smem_raw);
  const uint32_t bars = sb + BARS;
  const int tid = threadIdx.x, lane = tid & 31;
  const int cw = __shfl_sync(0xffffffffu, tid >> 5, 0), wg = cw >> 2, warp = cw & 3;
  const int bid = blockIdx.x, cl = bid >> 1, rank = bid & 1;
  const bool g2 = cl < 64;
  const int c4 = (cl + 60) & 63, gp = c4 < 32 ? (c4 & 7) : (c4 < 60 ? 1 + (c4 - 32) % 7 : 8), ix = c4 < 32 ? c4 >> 3 : (c4 < 60 ? (c4 - 32) / 7 : c4 - 60);
  const int tb2 = c4 < 32 ? gp : 7 + gp, db = ix;
  const int L = !g2 ? cl : (gp == 0 ? 56 + ix : (gp == 8 ? 60 + ix : 8 * (gp - 1) + ix + (c4 < 32 ? 0 : 4)));
  const int fb = L / 6, tb = 2 * (L % 6) + rank;
  const int g = lane >> 2, tig = lane & 3;
  const int dk = 128 * db + 64 * rank;

  uint32_t prm[7];
  if (wg < 2) {
    const int ch = g2 ? 4 * bid + (cw >> 1) : 0;
    const size_t po = (size_t)ch * 128 + 64 * (cw & 1) + 2 * lane;
#pragma unroll
    for (int i = 0; i < 6; i++) prm[i] = __ldg(reinterpret_cast<const uint32_t*>(P.ssm[i] + po));
    prm[6] = __bfloat16_as_ushort(P.logdt[ch]);
  }
  asm volatile("" ::: "memory");
  if (wg < 2) {
    if (tid < 120) {
      const uint32_t v = tid % 40 < 8 ? 0x3f803f80u : 0u;
      sts128(sb + (tid / 40) * G1_STG + 32768 + TB * 128 + (tid % 40) * 16, make_uint4(v, v, v, v));
    }
    fence_async_smem();
    asm volatile("barrier.cluster.arrive.relaxed.aligned;" ::: "memory");
    named_bar<0, 384>();
    cluster_wait();
    if (g2) {
      const float dt = bfr(expf(__uint_as_float(prm[6] << 16)));
      float kacc[6][4];
#pragma unroll
      for (int i = 0; i < 6; i++) { kacc[i][0] = kacc[i][1] = kacc[i][2] = kacc[i][3] = 0.f; }
      const uint32_t kst = cw < 7 ? sb + 2 * G1_STG + cw * KST : sb + STATS - KST + 1008;
      asm volatile("bar.arrive 7, 384;" ::"f"(dt) : "memory");
      C2 cc[2];
      cc[0] = cmul(C2{bflo(prm[4]), bflo(prm[5])}, C2{dt * bflo(prm[2]), dt * bflo(prm[3])});
      cc[1] = cmul(C2{bfhi(prm[4]), bfhi(prm[5])}, C2{dt * bfhi(prm[2]), dt * bfhi(prm[3])});
      const uint32_t cmax = __reduce_max_sync(0xffffffffu, __float_as_uint(fmaxf(fmaxf(fabsf(cc[0].x), fabsf(cc[0].y)), fmaxf(fabsf(cc[1].x), fabsf(cc[1].y)))));
      const uint32_t cexp = min(max(cmax >> 23, 2u), 252u);
      const float cscale = __uint_as_float((254u - cexp) << 23), cinv = __uint_as_float(cexp << 23);
      const bool grow = __any_sync(0xffffffffu, dt * fmaxf(bflo(prm[0]), bfhi(prm[0])) * 2048.f > 8.f);
#pragma unroll 1
      for (int c = 0; c < 2; c++) {
        auto pick = [&](uint32_t v) { return __uint_as_float(c ? (v & 0xffff0000u) : (v << 16)); };
        const float al = dt * pick(prm[0]) * 1.4426950408889634f, wr = dt * pick(prm[1]) * 0.15915494309189535f;
        const C2 c0 = C2{(c ? cc[1].x : cc[0].x) * cscale, (c ? cc[1].y : cc[0].y) * cscale};
        const uint32_t st = kst + lane * 4;
        auto put = [&](int row, __half2 v) { sts32(st + row * 144, *reinterpret_cast<uint32_t*>(&v)); };
        const C2 z8 = cexp_p(al, wr, 8.f), z1 = cexp_p(al, wr, 1.f), z256 = cexp_p(al, wr, 256.f);
        {
          const C2 z16 = csqr(z8), z32 = csqr(z16), z64 = csqr(z32), z128 = csqr(z64), z24 = cmul(z8, z16);
          const HZ h32 = tohzc(z32), h64 = tohzc(z64), h128 = tohzc(z128), h96 = tohzc(cmul(z32, z64));
          __half2 a[16];
          a[0] = __floats2half2_rn(1.f, 0.f); a[1] = tohzc(z8).z; a[2] = tohzc(z16).z; a[3] = tohzc(z24).z;
          a[4] = h32.z; a[8] = h64.z; a[12] = h96.z;
#pragma unroll
          for (int i = 1; i < 4; i++) { a[4 + i] = hmul(a[i], h32); a[8 + i] = hmul(a[i], h64); a[12 + i] = hmul(a[i], h96); }
#pragma unroll
          for (int i = 0; i < 16; i++) put(i, a[i]);
          put(16, h128.z);
#pragma unroll
          for (int i = 1; i < 16; i++) put(16 + i, hmul(a[i], h128));
        }
        {
          const C2 z2 = csqr(z1), z4 = csqr(z2), z512 = csqr(z256), z1024 = csqr(z512);
          const C2 e1 = cmul(c0, z2);
          const HZ h1 = tohz(z1), h256 = tohz(z256), h512 = tohz(z512), h768 = tohz(cmul(z512, z256));
          const __half2 e[4] = {toh(c0), toh(e1), toh(cmul(c0, z4)), toh(cmul(e1, z4))};
#pragma unroll
          for (int i = 0; i < 4; i++) { put(32 + 2 * i, e[i]); put(33 + 2 * i, hmul(e[i], h1)); put(40 + i, hmul(e[i], h256)); }
          put(44, hmul(e[0], h512)); put(45, hmul(e[2], h512)); put(46, hmul(e[0], h768)); put(47, hmul(e[2], h768));
          const C2 f = cmul(c0, z1024);
          const __half2 fh = toh(f);
          put(48, fh); put(49, hmul(fh, h256)); put(50, hmul(fh, h512)); put(51, hmul(fh, h768)); put(52, toh(cmul(f, z1024)));
        }
        __syncwarp();
#pragma unroll
        for (int s2 = 0; s2 < 2; s2++) {
          uint32_t a[4][4], b[3][4];
#pragma unroll
          for (int i = 0; i < 4; i++) ldsm4(a[i], kst + (16 * (i & 1) + (lane & 15)) * 144 + 16 * (lane >> 4) + 64 * s2 + 32 * (i >> 1));
#pragma unroll
          for (int i = 0; i < 3; i++) ldsm4(b[i], kst + (32 + 8 * i + (lane & 7)) * 144 + 16 * (lane >> 3) + 64 * s2);
#pragma unroll
          for (int k = 0; k < 2; k++)
#pragma unroll
            for (int i = 0; i < 6; i++) mma16816h(kacc[i], a[2 * k + (i & 1)], b[i >> 1][2 * k], b[i >> 1][2 * k + 1]);
        }
        __syncwarp();
      }
      if (cw >= 6) named_bar<4, 64>();
      const uint32_t kd = sb + CH0 + (cw >> 1) * CHS + C_KD + 3072 * (cw & 1) + 16 * lane;
#pragma unroll
      for (int i = 0; i < 6; i++)
        sts128(kd + 512 * i, make_uint4(__float_as_uint(kacc[i][0] * cinv), __float_as_uint(kacc[i][1] * cinv), __float_as_uint(kacc[i][2] * cinv), __float_as_uint(kacc[i][3] * cinv)));
      if (grow) {
#pragma unroll 1
        for (int i = 0; i < 24; i++) {
          const int col = 8 * (i >> 3) + 2 * tig + (i & 1);
          const int bb = col < 8 ? col : (col < 12 ? 240 + 2 * col : (col < 16 ? 512 + 256 * ((col - 12) >> 1) + 4 * (col & 1) : 256 * col - 3072));
          const float l = (float)(8 * (16 * ((i >> 2) & 1) + g + 8 * ((i >> 1) & 1)) + bb);
          float sum = 0.f;
#pragma unroll 1
          for (int m = 0; m < 64; m++) {
            const uint32_t ar = __shfl_sync(0xffffffffu, prm[0], m >> 1), ai = __shfl_sync(0xffffffffu, prm[1], m >> 1);
            const float cx = __shfl_sync(0xffffffffu, (m & 1) ? cc[1].x : cc[0].x, m >> 1), cy = __shfl_sync(0xffffffffu, (m & 1) ? cc[1].y : cc[0].y, m >> 1);
            const C2 z = cexp_p(dt * ((m & 1) ? bfhi(ar) : bflo(ar)) * 1.4426950408889634f, dt * ((m & 1) ? bfhi(ai) : bflo(ai)) * 0.15915494309189535f, l);
            sum += cx * z.x - cy * z.y;
          }
          sts32f(kd + 512 * (i >> 2) + 4 * (i & 3), sum);
        }
      }
    }
    __syncwarp();
    if (lane == 0) mbar_arrive(bars + 8 * B_KD);
    asm volatile("setmaxnreg.inc.sync.aligned.u32 208;");
    {
      float dg[88], du[88];
#pragma unroll 1
      for (int k = 0; k < 8; k++) {
        const int s = k % 3;
        mbar_wait(bars + 8 * (B_G1F + s), (k / 3) & 1);
        const uint32_t st = sb + s * G1_STG;
        const uint64_t da = mkdesc(st + wg * 8192, 8192, 1024), dbb = mkdesc(st + 32768, 16, 1024);
        WG_FENCE();
#pragma unroll
        for (int kk = 0; kk < 4; kk++) {
          wgmma_ss_n176<1, 0>(dg, da + kk * 128, dbb + kk * 2, (k | kk) != 0);
          wgmma_ss_n176<1, 0>(du, da + 1024 + kk * 128, dbb + kk * 2, (k | kk) != 0);
        }
        WG_COMMIT();
        WG_WAIT(1);
        if (k > 0 && (tid & 127) == 0) {
          mbar_arrive(bars + 8 * (B_G1E + (k + 2) % 3));
          if (k == 7) mbar_arrive(bars + 8 * B_Z);
        }
      }
      mbar_wait(bars + 8 * B_STATS, 0);
      mbar_wait(bars + 8 * (B_G1E + 2), 1);
      float4 s4[2];
      s4[0] = lds128f(sb + STATS + 16 * tig);
      s4[1] = lds128f(sb + STATS + 64 + 16 * tig);
      const uint32_t sa = sb + STAGING + wg * 22528 + ((lane & 7) + 8 * (lane >> 4)) * 128 + (((2 * warp + ((lane >> 3) & 1)) ^ ((lane + TB * tb) & 7)) << 4);
      WG_WAIT(0);
      fence_regs(dg);
      fence_regs(du);
      if ((tid & 127) == 0) mbar_arrive(bars + 8 * (B_G1E + 1));
      const int src = (lane & ~3) | 1;
      const float sg0 = __shfl_sync(0xffffffffu, dg[85], src), sg1 = __shfl_sync(0xffffffffu, dg[87], src);
      const float su0 = __shfl_sync(0xffffffffu, du[85], src), su1 = __shfl_sync(0xffffffffu, du[87], src);
#pragma unroll
      for (int i = 0; i < 24; i++) {
        if (i < 22) {
          const float4 q = s4[i & 1];
          dg[4 * i] = tanh_fast(fmaf(q.x, sg0, dg[4 * i]) * q.y);
          dg[4 * i + 1] = tanh_fast(fmaf(q.z, sg0, dg[4 * i + 1]) * q.w);
          dg[4 * i + 2] = tanh_fast(fmaf(q.x, sg1, dg[4 * i + 2]) * q.y);
          dg[4 * i + 3] = tanh_fast(fmaf(q.z, sg1, dg[4 * i + 3]) * q.w);
          du[4 * i] = fmaf(q.x, su0, du[4 * i]);
          du[4 * i + 1] = fmaf(q.z, su0, du[4 * i + 1]);
          du[4 * i + 2] = fmaf(q.x, su1, du[4 * i + 2]);
          du[4 * i + 3] = fmaf(q.z, su1, du[4 * i + 3]);
          if (i < 20) s4[i & 1] = lds128f(sb + STATS + 64 * (i + 2) + 16 * tig);
        }
        if (i >= 3 && (i & 1)) {
          const int j = 4 * (i - 3);
          uint32_t r[4];
#pragma unroll
          for (int e = 0; e < 4; e++) r[e] = pack2(fmaf(dg[j + 2 * e], du[j + 2 * e], du[j + 2 * e]), fmaf(dg[j + 2 * e + 1], du[j + 2 * e + 1], du[j + 2 * e + 1]));
          stsm4t(sa + (i - 3) * 1024, r[0], r[1], r[2], r[3]);
          if (i == 9 || i == 17 || i == 23) {
            fence_async_smem();
            __syncwarp();
            if (lane == 0) mbar_arrive(bars + 8 * (B_EPI + 3 * wg + (i >> 3) - 1 + (i == 23)));
          }
        }
      }
    }
    if (g2) {
      const uint32_t dw = __ldg(reinterpret_cast<const uint32_t*>(P.dskip + 4 * bid + 2 * wg));
      const float rs0 = 0.5f * __ldcg(&g_stats[128 * tb2 + 64 * wg + 16 * warp + g].y), rs1 = 0.5f * __ldcg(&g_stats[128 * tb2 + 64 * wg + 16 * warp + g + 8].y);
      float acc[64];
      const uint64_t da0 = mkdesc(sb + HRING + wg * 8192, 16, 1024), db0 = mkdesc(sb, 8192, 1024);
      {
        const int c = cw >> 1, be = cw & 1;
        const uint32_t w0 = sb + CH0 + c * CHS;
        const uint32_t rt = w0 + 4 * (g - 2 * tig) + 32;
        const uint32_t u0 = 2 * (lane & 15) + be + 32 * (lane >> 4);
        const uint32_t va = w0 + wof<WPL1>(u0), vb = w0 + wof<WPL1>(u0 + 1);
        mbar_wait(bars + 8 * B_TAB, 0);
        float acc[6][4];
#pragma unroll
        for (int i = 0; i < 6; i++) { acc[i][0] = acc[i][1] = acc[i][2] = acc[i][3] = 0.f; }
        phase_mma<2, 3>(acc, rt + C_P2, va + 16);
        phase_mma<2, 3>(acc, rt + C_P2 + 256, vb + 2 * WPL1);
        phase_mma<2, 3>(acc, rt + C_P2 + 512, vb);
        phase_mma<2, 3>(acc, rt + C_P2 + 768, va + 2 * WPL1);
        const uint32_t yo = 4 * (((16 * g + 2 * tig + 8 * be) ^ ((g & 2) << 2)) + 4 * (g >> 2));
        mbar_wait(bars + 8 * B_Y3, 0);
#pragma unroll
        for (int i = 0; i < 12; i++) {
          float u, v;
          asm volatile("ld.shared.v2.f32 {%0,%1}, [%2];" : "=f"(u), "=f"(v) : "r"(sb + Y3 + c * Y3CH + yo + 544 * i) : "memory");
          acc[i >> 1][2 * (i & 1)] += u;
          acc[i >> 1][2 * (i & 1) + 1] += v;
        }
        wg_bar(wg);
        if ((tid & 127) == 0) mbar_arrive(bars + 8 * B_Y);
#pragma unroll
        for (int i = 0; i < 12; i++) sts64f(w0 + yo + 544 * i, acc[i >> 1][2 * (i & 1)], acc[i >> 1][2 * (i & 1) + 1]);
      }
      {
        float y[2][16];
        uint32_t pq = sb + CH0 + 2 * wg * CHS + C_P01 + 4 * (g - 2 * tig) + 64 * warp + 32;
        const uint32_t dlo = (((sb + AUX + 2 * wg * XA + 1024 + 96) & 0x3FFFF) >> 4) | 0x10000u;
        const uint32_t zero = P.zero;
        int kb = 0;
#pragma unroll 1
        for (int ph = 0; ph < 2; ph++) {
          uint32_t q[3][6][4];
          uint32_t last[2] = {lds32(pq), lds32(pq + CHS)};
          auto ldq = [&](uint32_t (&d)[6][4], uint32_t o) {
#pragma unroll
            for (int i = 0; i < 6; i++) {
              const uint32_t e = pq + o + (i & 1) * CHS + (i >> 1) * 64;
              d[i][0] = lds32(e + 32); d[i][1] = lds32(e + 64);
            }
#pragma unroll
            for (int i = 0; i < 6; i++) {
              d[i][2] = copy_reg(last[i & 1], zero);
              d[i][3] = copy_reg(d[i][0], zero);
              last[i & 1] = d[i][1];
            }
          };
          ldq(q[0], 0);
#pragma unroll 1
          for (int it = ph ? DENSE_A : 0; it < (ph ? 4 : DENSE_A); it++) {
#pragma unroll
            for (int u = 0; u < 3; u++) {
              WG_FENCE();
#pragma unroll
              for (int i = 0; i < 6; i++)
                wgmma_rs_n32<0>(y[i & 1], q[u][i][0], q[u][i][1], q[u][i][2], q[u][i][3],
                                0x4000004000000000ull | (dlo + (i & 1) * (XA >> 4) - 18 * it - 6 * u - 2 * (i >> 1)), (it | u | (i >> 1)) != 0);
              WG_COMMIT();
              ldq(q[(u + 1) % 3], 192 + 192 * u);
              WG_WAIT(1);
            }
            pq += 576;
          }
          if (ph) {
            wg_bar(wg);
            uint32_t xr[2][2][4];
            float yp[2][12];
#pragma unroll
            for (int c = 0; c < 2; c++) {
              const uint32_t xb = sb + AUX + (2 * wg + c) * XA + 1024, yb = sb + CH0 + (2 * wg + c) * CHS + 4 * (136 * tig + 16 * warp + g), yx = (warp & 2) << 4;
#pragma unroll
              for (int i2 = 0; i2 < 2; i2++) ldsm4t(xr[c][i2], xb + (16 * i2 + 8 * (lane >> 4) + (lane & 7)) * 128 + (((2 * warp + ((lane >> 3) & 1)) ^ (lane & 7)) << 4));
#pragma unroll
              for (int i = 0; i < 12; i++) yp[c][i] = lds32f(yb + 2176 * (i >> 2) + ((32 * ((i >> 1) & 1)) ^ yx) + 272 * (i & 1));
            }
            WG_WAIT(0);
            fence_regs(y[0]);
            fence_regs(y[1]);
            wg_bar(wg);
            const uint32_t so = sb + AUX + 2 * wg * XA + 1024 + (8 * (lane >> 4) + (lane & 7)) * 128 + (((2 * warp + ((lane >> 3) & 1)) ^ (lane & 7)) << 4);
#pragma unroll
            for (int i = 0; i < 4; i++) {
              uint32_t o[4];
#pragma unroll
              for (int j = 0; j < 4; j++) {
                const int c = i >> 1, e = 4 * (i & 1) + j;
                float v0 = y[c][2 * e], v1 = y[c][2 * e + 1];
                if (e >= 2) { v0 += yp[c][2 * e - 4]; v1 += yp[c][2 * e - 3]; }
                asm("fma.rn.bf16x2 %0, %1, %2, %3;" : "=r"(o[j]) : "r"(xr[c][e >> 2][e & 3]), "r"(__byte_perm(dw, 0, c ? 0x3232 : 0x1010)), "r"(pack2(v0, v1)));
              }
              stsm4t(so + (i >> 1) * XA + (i & 1) * 2048, o[0], o[1], o[2], o[3]);
            }
            fence_async_smem();
            __syncwarp();
            if (lane == 0) mbar_arrive(bars + 8 * (B_SD + wg));
          }
#pragma unroll 1
          for (const int ke = ph ? 9 : G2P1; kb < ke; kb++) {
            const int ws = kb < 5 ? kb : kb - 5;
            mbar_wait(bars + 8 * (B_G2F + ws), kb >= 5);
            const uint64_t da = da0 + (ws < 3 ? ws + 2 : ws - 3) * 1024, dbb = db0 + ws * 1024;
            WG_FENCE();
#pragma unroll
            for (int kk = 0; kk < 4; kk++) wgmma_ss_n128<0, 1>(acc, da + kk * 2, dbb + kk * 128, (kb | kk) != 0);
            WG_COMMIT();
            WG_WAIT(1);
            if ((tid & 127) == 0) {
              if (kb > 0 && kb < 6 && kb != G2P1) mbar_arrive(bars + 8 * (B_G2E + kb - 1));
              if (kb == 6) asm volatile("mbarrier.arrive.shared::cluster.b64 _, [%0];" ::"r"(mapa(bars + 8 * B_PEER, rank ^ 1)) : "memory");
            }
          }
          WG_WAIT(0);
          fence_regs(acc);
          fence_regs(y[0]);
          fence_regs(y[1]);
          if (!ph && (tid & 127) == 0) mbar_arrive(bars + 8 * (B_G2E + G2P1 - 1));
        }
      }
      mbar_wait(bars + 8 * (B_G2F + 5), 0);
      mbar_wait(bars + 8 * (B_G2F + 4), 1);
      mbar_wait_cl(bars + 8 * B_PEER, 0);
      float keep[32], send[32];
#pragma unroll
      for (int i = 0; i < 32; i++) { keep[i] = acc[i]; send[i] = __uint_as_float(__float_as_uint(acc[32 + i]) | P.zero); }
      WG_FENCE();
#pragma unroll
      for (int kk = 0; kk < 8; kk++)
        wgmma_ss_n64<0, 1>(send, da0 + (kk < 4 ? 1024 : (XSLOT + 16384 - HRING) >> 4) + (kk & 3) * 2, db0 + (kk < 4 ? 4096 : XSLOT >> 4) + 512 + (kk & 3) * 128, 1);
      WG_COMMIT();
#pragma unroll
      for (int kk = 0; kk < 8; kk++)
        wgmma_ss_n64<0, 1>(keep, da0 + (kk < 4 ? 1024 : (XSLOT + 16384 - HRING) >> 4) + (kk & 3) * 2, db0 + (kk < 4 ? 4096 : XSLOT >> 4) + (kk & 3) * 128, 1);
      WG_COMMIT();
      const uint32_t rdst = mapa(sb + tid * 16, rank ^ 1), rbar = mapa(bars + 8 * B_RECV, rank ^ 1);
      const uint32_t xa = sb + AUX + (64 * wg + 16 * warp + (lane & 15)) * 128;
      const uint32_t sa = sb + AUX + 16384 + wg * 8192 + ((lane & 7) + 8 * (lane >> 4)) * 128 + (((2 * warp + ((lane >> 3) & 1)) ^ (lane & 7)) << 4);
      WG_WAIT(1);
      fence_regs(send);
#pragma unroll
      for (int j = 0; j < 4; j++)
        asm volatile("st.async.weak.shared::cluster.mbarrier::complete_tx::bytes.v4.b32 [%0], {%1,%2,%3,%4}, [%5];" ::"r"(rdst + j * 4096),
                     "r"(pack2(send[8 * j], send[8 * j + 1])), "r"(pack2(send[8 * j + 2], send[8 * j + 3])), "r"(pack2(send[8 * j + 4], send[8 * j + 5])),
                     "r"(pack2(send[8 * j + 6], send[8 * j + 7])), "r"(rbar) : "memory");
      WG_WAIT(0);
      fence_regs(keep);
      mbar_wait_cl(bars + 8 * B_RECV, 0);
      float th[32];
#pragma unroll
      for (int i = 0; i < 4; i++) {
        const uint4 p = lds128(sb + i * 4096 + tid * 16);
        const uint32_t pw[4] = {p.x, p.y, p.z, p.w};
#pragma unroll
        for (int e = 0; e < 4; e++) {
          keep[8 * i + 2 * e] = ((e & 1) ? rs1 : rs0) * (keep[8 * i + 2 * e] + bflo(pw[e]));
          keep[8 * i + 2 * e + 1] = ((e & 1) ? rs1 : rs0) * (keep[8 * i + 2 * e + 1] + bfhi(pw[e]));
        }
      }
#pragma unroll
      for (int i = 0; i < 32; i++) th[i] = tanh_fast(keep[i]);
      mbar_wait(bars + 8 * B_XS, 0);
      uint32_t xr[4][4], sr[4][4];
#pragma unroll
      for (int i2 = 0; i2 < 4; i2++) {
        ldsm4(xr[i2], xa + (((2 * i2 + (lane >> 4)) ^ (lane & 7)) << 4));
        ldsm4t(sr[i2], sa + i2 * 2048);
      }
#pragma unroll
      for (int i2 = 0; i2 < 4; i2++) {
        uint32_t o[4];
#pragma unroll
        for (int e = 0; e < 4; e++) {
          const int j = 8 * i2 + 2 * e;
          asm("fma.rn.bf16x2 %0, %1, %2, %3;" : "=r"(o[e]) : "r"(sr[i2][e]), "r"(pack2(fmaf(th[j], keep[j], keep[j]), fmaf(th[j + 1], keep[j + 1], keep[j + 1]))), "r"(xr[i2][e]));
        }
        stsm4(xa + (((2 * i2 + (lane >> 4)) ^ (lane & 7)) << 4), o[0], o[1], o[2], o[3]);
      }
      __syncwarp();
      {
        const int r4 = lane >> 3, c8 = lane & 7;
        __nv_bfloat16* dst = P.out + (size_t)(128 * tb2 + 64 * wg + 16 * warp + r4) * D_ + dk + 8 * c8;
#pragma unroll
        for (int i = 0; i < 4; i++) {
          const uint4 v = lds128(sb + AUX + (64 * wg + 16 * warp + 4 * i + r4) * 128 + ((c8 ^ ((4 * i + r4) & 7)) << 4));
          *reinterpret_cast<uint4*>(dst + 4 * i * D_) = v;
        }
      }
    }
  } else if (wg == 3) {
    asm volatile("setmaxnreg.dec.sync.aligned.u32 24;");
    if (elect()) {
      if (warp < 3) prefetch_map(&P.x1 + warp);
#pragma unroll 1
      for (int i = warp; i < B_COUNT; i += 4) mbar_init(bars + 8 * i, i < B_G2F ? 1 : (i < B_STATS ? 2 : (i < B_KD ? 4 : 8)));
      asm volatile("fence.mbarrier_init.release.cluster;" ::: "memory");
      if (warp < 2) mbar_expect_tx(bars + 8 * (B_G1F + warp), G1_TX);
      if (warp == 0) mbar_expect_tx(bars + 8 * B_RECV, 16384);
    }
    named_bar<5, 128>();
    asm volatile("bar.arrive 0, 384;" ::: "memory");
    asm volatile("bar.arrive 6, 256;" ::: "memory");
    asm volatile("barrier.cluster.arrive.relaxed.aligned;" ::: "memory");
    if (elect()) {
      if (warp == 0) {
        tma2d(sb + 32768, &P.x1, bars + 8 * B_G1F, 0, TB * tb);
        tma2d(sb + G1_STG + 32768, &P.x1, bars + 8 * (B_G1F + 1), 64, TB * tb);
        mbar_wait(bars + 8 * B_KD, 0);
#pragma unroll 1
        for (int k = 2; k < 8; k++) {
          const int s = k % 3;
          const uint32_t st = sb + s * G1_STG, bar = bars + 8 * (B_G1F + s);
          if (k > 2) mbar_wait(bars + 8 * (B_G1E + s), (k / 3 - 1) & 1);
          mbar_expect_tx(bar, G1_TX);
          tma2d(st + 32768, &P.x1, bar, 64 * k, TB * tb);
#pragma unroll 1
          for (int i = 0; i < 4; i++) tma2d(st + i * 8192, &P.wg + (i >> 1), bar, 128 * fb + 64 * (i & 1), 64 * k);
        }
        if (g2) {
          mbar_wait(bars + 8 * B_STG, 0);
          poll_ge(&g_cnt[(C_H + 2 * ((128 * tb2) / TB) + rank) * 32], &g_cnt[(C_H + 2 * ((128 * tb2 + 127) / TB) + rank) * 32], 11);
          fence_async_global();
#pragma unroll 1
          for (int kb = 0; kb < 11; kb++) {
            const int ws = kb < 5 ? kb : (kb < 9 ? kb - 5 : 14 - kb);
            const uint32_t bar = bars + 8 * (B_G2F + ws);
            if (kb == 9) { mbar_wait(bars + 8 * B_SD, 0); mbar_wait(bars + 8 * (B_SD + 1), 0); }
            else if (kb >= 5) mbar_wait(bars + 8 * (B_G2E + ws), 0);
            mbar_expect_tx(bar, 16384);
            asm volatile("cp.async.bulk.shared::cluster.global.mbarrier::complete_tx::bytes [%0], [%1], %2, [%3];" ::"r"(sb + (ws < 5 ? HRING + (ws < 3 ? ws + 2 : ws - 3) * 16384 : XSLOT + 16384)),
                         "l"(g_h + ((size_t)(11 * rank + kb) * T_ + 128 * tb2) * 64), "r"(16384), "r"(bar) : "memory");
          }
        }
        mbar_wait(bars + 8 * (g2 ? B_XS : B_STATS), 0);
        const unsigned prev = atomicAdd(&g_cnt[C_DONE * 32], 1u);
        if (prev == gridDim.x - 1) {
#pragma unroll 1
          for (int i = 0; i < C_COUNT; i++) g_cnt[i * 32] = 0;
        }
      } else if (warp < 3) {
#pragma unroll 1
        for (int i = 0; i < 4; i++)
          tma2d(sb + (i >> 1) * G1_STG + (warp - 1) * 16384 + (i & 1) * 8192, &P.x1 + warp, bars + 8 * (B_G1F + (i >> 1)), 128 * fb + 64 * (i & 1), 64 * (i >> 1));
#pragma unroll 1
        for (int i = 0; i < 3; i++) {
          mbar_wait(bars + 8 * (B_EPI + 3 * (warp - 1) + i), 0);
          asm volatile("cp.async.bulk.global.shared::cta.bulk_group [%0], [%1], %2;" ::"l"(g_h + ((size_t)(2 * fb + warp - 1) * T_ + TB * tb + 64 * i) * 64),
                       "r"(sb + STAGING + (warp - 1) * 22528 + 8192 * i), "r"(i < 2 ? 8192 : (tb < 11 ? 43 * 128 : 39 * 128)) : "memory");
        }
        bulk_commit();
        bulk_wait0();
        red_arrive(&g_cnt[(C_H + 2 * tb + (2 * fb + warp - 1 > 10)) * 32]);
        mbar_arrive(bars + 8 * B_STG);
        if (g2) {
          mbar_wait(bars + 8 * (B_SD + warp - 1), 0);
#pragma unroll 1
          for (int i = 2 * warp - 2; i < 2 * warp; i++)
            tma2d_store(&P.ss, sb + AUX + i * XA + 1024, 0, 32 * (4 * bid + i));
          bulk_commit();
          bulk_wait0();
          red_arrive(&g_cnt[(C_S + (bid >> 4)) * 32]);
          mbar_arrive(bars + 8 * B_AUXD);
          if (warp == 1) {
            mbar_wait(bars + 8 * B_AUXD, 0);
            mbar_expect_tx(bars + 8 * B_XS, 32768);
            tma2d(sb + AUX, &P.x2, bars + 8 * B_XS, dk, 128 * tb2);
            poll_ge(&g_cnt[(C_S + 2 * db + rank) * 32], 32);
            fence_async_global();
            tma2d(sb + AUX + 16384, &P.st, bars + 8 * B_XS, 128 * tb2, dk);
            tma2d(sb + AUX + 24576, &P.st, bars + 8 * B_XS, 128 * tb2 + 64, dk);
          }
        }
      } else {
#pragma unroll 1
        for (int i = 3; i < 9; i++) prefetch_map(&P.x1 + i);
        if (g2) {
          mbar_wait(bars + 8 * B_LN, 0);
          red_arrive(&g_cnt[C_LN * 32]);
        }
        poll_ge(&g_cnt[C_LN * 32], 128);
        fence_async_global();
#pragma unroll 1
        for (int i = 0; i < 4; i++) {
          if (g2) {
            mbar_expect_tx(bars + 8 * (B_X + i), 4096);
            tma2d(sb + AUX + i * XA + 1024, &P.xl, bars + 8 * (B_X + i), 0, 32 * (4 * bid + i));
          } else {
            mbar_arrive(bars + 8 * (B_X + i));
          }
        }
        if (g2) {
          if (bid < 126)
            asm volatile("cp.async.bulk.prefetch.L2.global [%0], %1;" ::"l"(P.wdp + (size_t)bid * 11 * D_), "r"(bid < 125 ? 11 * 1024 : 1024) : "memory");
#pragma unroll 1
          for (int kb = 0; kb < 11; kb++) {
            const int ws = kb < 5 ? kb : (kb < 9 ? kb - 5 : 14 - kb);
            const uint32_t bar = bars + 8 * (B_G2F + ws), dst = sb + (ws < 5 ? ws * 16384 : XSLOT);
            if (kb == 0) mbar_wait(bars + 8 * B_Z, 0);
            if (kb == 2) mbar_wait(bars + 8 * B_Y, 0);
            if (kb == 9) { mbar_wait(bars + 8 * B_SD, 0); mbar_wait(bars + 8 * (B_SD + 1), 0); }
            else if (kb >= 5) mbar_wait(bars + 8 * (B_G2E + ws), 0);
            mbar_expect_tx(bar, 16384);
            tma2d(dst, &P.wd, bar, dk, 704 * rank + 64 * kb);
            tma2d(dst + 8192, &P.wd, bar, dk ^ 64, 704 * rank + 64 * kb);
          }
        }
      }
    }
  } else {
    asm volatile("setmaxnreg.dec.sync.aligned.u32 72;");
    asm volatile("barrier.cluster.arrive.relaxed.aligned;" ::: "memory");
    const uint32_t xw = sb + AUX + warp * XA, w0 = sb + CH0 + warp * CHS;
    const int ch = 4 * bid + warp;
    const int t0 = TB * tb + tid - 256;
    named_bar<6, 256>();
    if (g2) {
      uint4 xv[4][2];
      named_bar<7, 384>();
#pragma unroll
      for (int j = 0; j < 4; j++) {
        const uint4* p = reinterpret_cast<const uint4*>(P.x + (size_t)(16 * bid + 4 * warp + j) * D_);
        xv[j][0] = __ldg(p + lane);
        xv[j][1] = __ldg(p + 32 + lane);
      }
      {
        float s1[4], s2[4], c0[4];
#pragma unroll
        for (int j = 0; j < 4; j++) {
          c0[j] = __shfl_sync(0xffffffffu, bflo(xv[j][0].x), 0);
          float f[16];
          unpack8(f, xv[j][0]);
          unpack8(f + 8, xv[j][1]);
          float a0 = 0.f, a1 = 0.f, q0 = 0.f, q1 = 0.f;
#pragma unroll
          for (int e = 0; e < 8; e++) {
            const float d0 = f[2 * e] - c0[j], d1 = f[2 * e + 1] - c0[j];
            a0 += d0; a1 += d1;
            q0 = fmaf(d0, d0, q0); q1 = fmaf(d1, d1, q1);
          }
          s1[j] = a0 + a1; s2[j] = q0 + q1;
        }
        {
          const bool b0 = lane & 1, b1 = lane & 2, b2 = lane & 4;
          float t[4], u[2], v;
#pragma unroll
          for (int j = 0; j < 4; j++) t[j] = (b0 ? s2[j] : s1[j]) + __shfl_xor_sync(0xffffffffu, b0 ? s1[j] : s2[j], 1);
#pragma unroll
          for (int j = 0; j < 2; j++) u[j] = (b1 ? t[2 * j + 1] : t[2 * j]) + __shfl_xor_sync(0xffffffffu, b1 ? t[2 * j] : t[2 * j + 1], 2);
          v = (b2 ? u[1] : u[0]) + __shfl_xor_sync(0xffffffffu, b2 ? u[0] : u[1], 4);
          v += __shfl_xor_sync(0xffffffffu, v, 8);
          v += __shfl_xor_sync(0xffffffffu, v, 16);
          const float o = __shfl_xor_sync(0xffffffffu, v, 1);
          const float cj = b2 ? (b1 ? c0[3] : c0[2]) : (b1 ? c0[1] : c0[0]);
          const float md = (b0 ? o : v) * (1.f / D_);
          const float var = fmaxf(fmaf(-md, md, (b0 ? v : o) * (1.f / D_)), 0.f);
          const float m = bfr(cj + md);
          float sq, inv;
          asm("sqrt.approx.f32 %0, %1;" : "=f"(sq) : "f"(bfr(bfr(var) + 1e-5f)));
          asm("rcp.approx.f32 %0, %1;" : "=f"(inv) : "f"(bfr(sq)));
          if (lane < 8 && !b0) sts64f(xw + 4 * lane, -m, 0.5f * inv);
          v = b0 ? inv : m;
#pragma unroll
          for (int j = 0; j < 4; j++) { s1[j] = __shfl_sync(0xffffffffu, v, 2 * j); s2[j] = __shfl_sync(0xffffffffu, v, 2 * j + 1); }
        }
#pragma unroll
        for (int j = 0; j < 4; j++) {
          const uint32_t m2 = pack2(s1[j], s1[j]);
          uint32_t w_[8] = {xv[j][0].x, xv[j][0].y, xv[j][0].z, xv[j][0].w, xv[j][1].x, xv[j][1].y, xv[j][1].z, xv[j][1].w};
#pragma unroll
          for (int e = 0; e < 8; e++) {
            const uint32_t d = hsub(w_[e], m2);
            w_[e] = pack2(bflo(d) * s2[j], bfhi(d) * s2[j]);
          }
          const uint32_t row = w0 + 32 * warp + j * 1040 + lane * 16;
          sts128(row, make_uint4(w_[0], w_[1], w_[2], w_[3]));
          sts128(row + 512, make_uint4(w_[4], w_[5], w_[6], w_[7]));
        }
      }
      named_bar<1, 128>();
      {
        const uint32_t src = sb + CH0 + ((lane & 7) >> 1) * (CHS + 32) + ((lane & 1) + 2 * ((lane >> 3) & 1)) * 1040 + (16 * warp + (lane >> 4)) * 16;
        const uint32_t dst = xw + 1024 + g * 32 + tig * 8;
#pragma unroll 2
        for (int i = 0; i < 8; i++) {
          uint32_t r[4];
          ldsm4t(r, src + 32 * i);
          asm volatile("st.shared.v2.u32 [%0], {%1,%2};" ::"r"(dst + 512 * i), "r"(r[0]), "r"(r[1]) : "memory");
          asm volatile("st.shared.v2.u32 [%0], {%1,%2};" ::"r"(dst + 512 * i + 256), "r"(r[2]), "r"(r[3]) : "memory");
        }
      }
      fence_async_smem();
      __syncwarp();
      if (elect()) {
        tma2d_store(&P.xt, xw + 1024, 16 * bid, 128 * warp);
        asm volatile("cp.async.bulk.global.shared::cta.bulk_group [%0], [%1], %2;" ::"l"(g_stats + 16 * bid + 4 * warp), "r"(xw), "r"(32) : "memory");
        bulk_commit();
        bulk_wait0();
        mbar_arrive(bars + 8 * B_LN);
      }
      __syncwarp();
    }
    mbar_wait(bars + 8 * B_KD, 0);
    if (g2) {
      {
        float k[6][4];
#pragma unroll
        for (int i = 0; i < 6; i++) {
          const float4 a = lds128f(w0 + C_KD + 512 * i + 16 * lane), b = lds128f(w0 + C_KD + 3072 + 512 * i + 16 * lane);
          k[i][0] = a.x + b.x; k[i][1] = a.y + b.y; k[i][2] = a.z + b.z; k[i][3] = a.w + b.w;
        }
        __syncwarp();
#pragma unroll 1
        for (int i = lane; i < 264; i += 32) sts128(w0 + C_P01 + 16 * i, make_uint4(0, 0, 0, 0));
        __syncwarp();
        const uint32_t p01 = w0 + C_P01 + 256;
        if (lane == 2) {
          sts16(p01 + 4 * 511, (uint16_t)pack2(k[2][0], 0.f));
          sts16(p01 + 4 * 512 + 2, (uint16_t)pack2(k[2][0], 0.f));
          sts16(w0 + C_P3 + 320 + 4 * 79, (uint16_t)pack2(k[4][0], 0.f));
          sts32f(w0 + C_KS, k[2][0]);
        }
        if (lane == 0) sts32f(w0 + C_KS + 4, k[4][0]);
#pragma unroll 1
        for (int r = 3; r >= 0; r--) {
          const int j = g + 8 * r;
          const uint32_t v01 = pack2(k[3][2], k[3][3]);
          if (tig < 2) {
            const uint32_t e = p01 + 4 * (256 + 8 * j + 4 * tig);
            const uint32_t aa = pack2(k[3][2], k[3][2]);
            asm volatile("st.shared.v2.u32 [%0], {%1,%1};" ::"r"(e), "r"(aa) : "memory");
            sts32(e + 8, pack2(k[3][3], k[3][2]));
            sts16(e - 4, (uint16_t)aa);
            sts16(e + 14, (uint16_t)(v01 >> 16));
            const uint32_t w01 = pack2(k[5][2], k[5][3]);
            const uint32_t e3 = w0 + C_P3 + 4 * (16 + 32 * tig + (j >> 1)) + ((j & 1) ? 0 : 320 - 4);
            if (r || lane) { sts16(e3, (uint16_t)w01); sts16(e3 + 6, (uint16_t)w01); }
            sts16(e3 + 64, (uint16_t)(w01 >> 16));
            if (r < 3 || lane != 29) sts16(e3 + 70, (uint16_t)(w01 >> 16));
          } else {
            const uint32_t e2 = w0 + C_P2 + 4 * (16 * (tig - 1) + (j >> 1));
            const uint32_t ea = (j & 1) ? e2 + 256 : e2 + 768 - 4, eb = (j & 1) ? e2 + 512 : e2;
            if (r || lane != 2) { sts16(ea, (uint16_t)v01); sts16(ea + 6, (uint16_t)v01); }
            sts16(eb, (uint16_t)(v01 >> 16)); sts16(eb + 6, (uint16_t)(v01 >> 16));
          }
#pragma unroll
          for (int i = 1; i < 3; i++) {
            k[2 * i + 1][2] = k[2 * i + 1][0]; k[2 * i + 1][3] = k[2 * i + 1][1];
            k[2 * i + 1][0] = k[2 * i][2]; k[2 * i + 1][1] = k[2 * i][3];
            k[2 * i][2] = k[2 * i][0]; k[2 * i][3] = k[2 * i][1];
          }
        }
        __syncwarp();
#pragma unroll
        for (int r = 0; r < 4; r++) {
          const uint32_t e = p01 + 4 * (8 * (g + 8 * r) + 2 * tig);
          const uint32_t v = pack2(k[r >> 1][2 * (r & 1) + 1], k[r >> 1][2 * (r & 1)]);
          sts32(e + 4, v);
          sts16(e, (uint16_t)(v >> 16));
          sts16(e + 10, (uint16_t)v);
        }
      }
      sts128(xw + lane * 16, make_uint4(0, 0, 0, 0));
      sts128(xw + 512 + lane * 16, make_uint4(0, 0, 0, 0));
      named_bar<1, 128>();
    }
    mbar_wait(bars + 8 * (B_X + warp), 0);
    float2 sa = make_float2(0.f, 0.f), sc = sa;
    if (t0 < T_) sa = __ldcg(&g_stats[t0]);
    if (tid - 256 < 43 && t0 + 128 < T_) sc = __ldcg(&g_stats[t0 + 128]);
    if (g2) {
      uint4 v0, v1 = lds128(xw + xof(5 * lane + 61)), v2 = lds128(xw + xof(5 * lane + 62)), v3 = lds128(xw + xof(5 * lane + 63));
#pragma unroll 1
      for (int u = 5 * lane; u < 5 * lane + 5; u++) {
        v0 = v1; v1 = v2; v2 = v3;
        v3 = lds128(xw + xof(u + 64));
        const uint32_t a[8] = {v0.z, v0.w, v1.x, v1.y, v1.z, v1.w, v2.x, v2.y};
        uint32_t p2[7], p4[6], o0[4], o1[4];
#pragma unroll
        for (int k = 0; k < 7; k++) p2[k] = hadd(a[k], mid(a[k], a[k + 1]));
#pragma unroll
        for (int k = 0; k < 6; k++) p4[k] = hadd(p2[k], p2[k + 1]);
#pragma unroll
        for (int k = 0; k < 4; k++) {
          const uint32_t s8 = hadd(p4[k], p4[k + 2]);
          o0[k] = hsub(s8, a[k]);
          o1[k] = hadd(s8, a[k + 4]);
        }
        if (u < 130) {
          sts128(w0 + wof<WPL0>(u), make_uint4(o0[0], o0[1], o0[2], o0[3]));
          sts128(w0 + 2 * WPL0 + wof<WPL0>(u), make_uint4(o1[0], o1[1], o1[2], o1[3]));
        }
      }
      fence_async_smem();
      v1 = lds128(xw + xof(7 * lane + 62)); v2 = lds128(xw + xof(7 * lane + 63)); v3 = lds128(xw + xof(7 * lane + 64));
      sts64f(sb + STATS + 8 * (tid - 256), sa.x, sa.y);
      if (tid - 256 < 48) sts64f(sb + STATS + 8 * (tid - 128), sc.x, sc.y);
      __syncwarp();
      if (elect()) {
        asm volatile("cp.async.bulk.global.shared::cta.bulk_group [%0], [%1], %2;" ::"l"(g_w79 + (size_t)ch * ZCH), "r"(w0), "r"(ZCH) : "memory");
        bulk_commit();
        mbar_arrive(bars + 8 * B_STATS);
        bulk_wait0_read();
      }
      __syncwarp();
#pragma unroll 1
      for (int u = 7 * lane + 2; u < 7 * lane + 9; u++) {
        v0 = v1; v1 = v2; v2 = v3;
        v3 = lds128(xw + xof(u + 63));
        const uint32_t a[8] = {v0.w, v1.x, v1.y, v1.z, v1.w, v2.x, v2.y, v2.z};
        uint32_t m[7], s3[6];
#pragma unroll
        for (int k = 0; k < 7; k++) m[k] = mid(a[k], a[k + 1]);
#pragma unroll
        for (int k = 0; k < 6; k++) s3[k] = hadd(hadd(m[k], m[k + 1]), a[k + 1]);
        if (u < 196) {
          sts128(w0 + wof<WPL1>(u), make_uint4(s3[2], s3[3], s3[4], s3[5]));
          sts128(w0 + 2 * WPL1 + wof<WPL1>(u - 1), make_uint4(hadd(s3[0], hadd(a[0], a[2])), hadd(s3[1], hadd(a[1], a[3])), hadd(s3[2], hadd(a[2], a[4])), hadd(s3[3], hadd(a[3], a[5]))));
        }
      }
      if (lane < 2) sts128(w0 + WPL1 * (1 + lane), make_uint4(0, 0, 0, 0));
      fence_async_smem();
      __syncwarp();
      if (lane == 0) mbar_arrive(bars + 8 * B_TAB);
      const uint32_t z0 = sb + ZONE + warp * ZCH;
      if (elect()) {
        bulk_wait0();
        mbar_wait(bars + 8 * B_Z, 0);
        mbar_expect_tx(bars + 8 * (B_X + warp), ZCH);
        asm volatile("cp.async.bulk.shared::cluster.global.mbarrier::complete_tx::bytes [%0], [%1], %2, [%3];" ::"r"(z0), "l"(g_w79 + (size_t)ch * ZCH), "r"(ZCH),
                     "r"(bars + 8 * (B_X + warp)) : "memory");
      }
      __syncwarp();
      mbar_wait(bars + 8 * (B_X + warp), 1);
      mbar_wait(bars + 8 * (B_G1E + 1), 0);
      const float k512 = lds32f(w0 + C_KS), k1024 = lds32f(w0 + C_KS + 4);
#pragma unroll 1
      for (int be = 0; be < 2; be++) {
        const uint32_t rt = w0 + 4 * (g - 2 * tig) + 32, u0 = 2 * (lane & 15) + be + 32 * (lane >> 4);
        float acc[6][4];
#pragma unroll
        for (int i = 0; i < 6; i++) { acc[i][0] = acc[i][1] = acc[i][2] = acc[i][3] = 0.f; }
        phase_mma<4, 4>(acc, rt + C_P3, z0 + wof<WPL0>(u0 + 1));
        phase_mma<4, 4>(acc, rt + C_P3 + 320, z0 + 2 * WPL0 + wof<WPL0>(u0));
#pragma unroll
        for (int e = 0; e < 2; e++) {
          const uint32_t l3 = 2 * tig + e + 3, l7 = l3 + 4;
          const uint32_t a3 = w0 + wof<WPL1>(2 * g + be + 2 + (l3 >> 3)) + (l3 & 7) * 2;
          const uint32_t a7 = z0 + wof<WPL0>(2 * g + be + 1 + (l7 >> 3)) + (l7 & 7) * 2;
#pragma unroll
          for (int i = 0; i < 12; i++) {
            float& y = acc[i >> 1][2 * (i & 1) + e];
            y = fmaf(k512, lds16bf(a3 + 128 * i), y);
            if (i >= 4) y = fmaf(k1024, lds16bf(a7 + 128 * (i - 4)), y);
          }
          if (be == 1 && g == 7) acc[1][2 + e] = fmaf(k1024, lds16bf(a7 - 128), acc[1][2 + e]);
        }
        const uint32_t yb = sb + Y3 + warp * Y3CH + 4 * (((16 * g + 2 * tig + 8 * be) ^ ((g & 2) << 2)) + 4 * (g >> 2));
#pragma unroll
        for (int i = 0; i < 12; i++) sts64f(yb + 544 * i, acc[i >> 1][2 * (i & 1)], acc[i >> 1][2 * (i & 1) + 1]);
      }
      __syncwarp();
      if (lane == 0) mbar_arrive(bars + 8 * B_Y3);
    } else {
      sts64f(sb + STATS + 8 * (tid - 256), sa.x, sa.y);
      if (tid - 256 < 48) sts64f(sb + STATS + 8 * (tid - 128), sc.x, sc.y);
      __syncwarp();
      if (lane == 0) mbar_arrive(bars + 8 * B_STATS);
    }
  }
}

typedef CUresult (*EncFn)(CUtensorMap*, CUtensorMapDataType, cuuint32_t, void*, const cuuint64_t*, const cuuint64_t*, const cuuint32_t*,
                          const cuuint32_t*, CUtensorMapInterleave, CUtensorMapSwizzle, CUtensorMapL2promotion, CUtensorMapFloatOOBfill);

void make_map(EncFn enc, CUtensorMap* m, const void* base, int cols, int rows, int box_rows, int box_cols = 64) {
  cuuint64_t gd[2] = {(cuuint64_t)cols, (cuuint64_t)rows};
  cuuint64_t gs[1] = {(cuuint64_t)cols * 2};
  cuuint32_t bx[2] = {(cuuint32_t)box_cols, (cuuint32_t)box_rows};
  cuuint32_t es[2] = {1, 1};
  enc(m, CU_TENSOR_MAP_DATA_TYPE_BFLOAT16, 2, const_cast<void*>(base), gd, gs, bx, es, CU_TENSOR_MAP_INTERLEAVE_NONE,
      box_cols == 64 ? CU_TENSOR_MAP_SWIZZLE_128B : CU_TENSOR_MAP_SWIZZLE_NONE, CU_TENSOR_MAP_L2_PROMOTION_L2_128B, CU_TENSOR_MAP_FLOAT_OOB_FILL_NONE);
}

}

extern "C" void kernel_launch(void* const* d_in, const int* in_sizes, int n_in, void* d_out, int out_size) {
  (void)in_sizes; (void)n_in; (void)out_size;
  void* fn = nullptr;
  cudaDriverEntryPointQueryResult q;
  cudaGetDriverEntryPoint("cuTensorMapEncodeTiled", &fn, cudaEnableDefault, &q);
  EncFn enc = (EncFn)fn;
  void *ps, *px;
  cudaGetSymbolAddress(&px, g_xnT);
  cudaGetSymbolAddress(&ps, g_sT);
  typedef const __nv_bfloat16* BP;
  Params P;
  make_map(enc, &P.x1, d_in[0], D_, T_, TB);
  make_map(enc, &P.x2, d_in[0], D_, T_, 128);
  make_map(enc, &P.wg, d_in[10], F_, D_, 64);
  make_map(enc, &P.wu, d_in[11], F_, D_, 64);
  make_map(enc, &P.wd, d_in[12], D_, F_, 64);
  make_map(enc, &P.st, ps, T_, D_, 64);
  P.out = (__nv_bfloat16*)d_out;
  make_map(enc, &P.xt, px, T_, D_, 128, 16);
  make_map(enc, &P.xl, px, 64, D_ * 32, 32);
  make_map(enc, &P.ss, ps, 64, D_ * 32, 32);
  for (int i = 0; i < 6; i++) P.ssm[i] = (BP)d_in[1 + i];
  P.zero = 0;
  P.x = (BP)d_in[0]; P.logdt = (BP)d_in[7]; P.dskip = (BP)d_in[8]; P.wdp = (BP)d_in[12];
  cudaFuncSetAttribute(fused_kernel, cudaFuncAttributeMaxDynamicSharedMemorySize, SMEM_BYTES);
  cudaLaunchConfig_t cfg = {};
  cfg.gridDim = dim3(132);
  cfg.blockDim = dim3(512);
  cfg.dynamicSmemBytes = SMEM_BYTES;
  cfg.stream = cudaStreamPerThread;
  cudaLaunchAttribute at[1];
  at[0].id = cudaLaunchAttributeClusterDimension;
  at[0].val.clusterDim.x = 2; at[0].val.clusterDim.y = 1; at[0].val.clusterDim.z = 1;
  cfg.attrs = at;
  cfg.numAttrs = 1;
  cudaLaunchKernelEx(&cfg, fused_kernel, P);
}
```
